```python
import torch

def _softmax(x, axis=-1):
    return torch.softmax(x, dim=axis)
def _gelu(x):
    return torch.nn.functional.gelu(x, approximate="tanh")
def _silu(x):
    return torch.nn.functional.silu(x)
def _sigmoid(x):
    return torch.sigmoid(x)
def _layernorm(x, axis=-1, eps=1e-5):
    m = x.mean(dim=axis, keepdim=True)
    v = x.var(dim=axis, keepdim=True, unbiased=False)
    return (x - m) / torch.sqrt(v + eps)
def _scatter_add(tgt, idx, src, axis=0):
    return tgt.clone().index_add_(axis, idx, src)
def _segment_sum(src, seg, n):
    out = torch.zeros((n,) + src.shape[1:], dtype=src.dtype)
    return out.index_add_(0, seg, src)
def _pad(x, pw):
    flat = tuple(v for pair in reversed(pw) for v in pair)
    return torch.nn.functional.pad(x, flat)

kernel_name = 'standalone__gqa_softmax__near_ridge'

def setup_inputs():

    _w = (lambda a: (lambda t: t.to(torch.bfloat16) if t.is_floating_point() else t)(torch.as_tensor(a)))
    B, Hq, Hkv, Sq, Sk, D = 8, 16, 8, 144, 1024, 256
    return {
        "q": _w((lambda *s: torch.randn(*s, dtype=torch.bfloat16) * 0.8)(B, Hq, Sq, D)),
        "k": _w((lambda *s: torch.randn(*s, dtype=torch.bfloat16) * 0.8)(B, Hkv, Sk, D)),
        "v": _w((lambda *s: torch.randn(*s, dtype=torch.bfloat16) * 0.05)(B, Hkv, Sk, D)),
    }

def reference(q, k, v):
    B, Hq, Sq, D = q.shape
    Hkv = k.shape[1]
    rep = Hq // Hkv
    k = (lambda x, n, axis: torch.repeat_interleave(x, n, dim=axis))(k, rep, axis=1)
    v = (lambda x, n, axis: torch.repeat_interleave(x, n, dim=axis))(v, rep, axis=1)
    scale = D ** -0.5
    scores = torch.einsum("bhqd,bhkd->bhqk", q, k) * scale
    p = _softmax(scores, axis=-1)
    return torch.einsum("bhqk,bhkd->bhqd", p, v)
```

```cpp
#include <cuda_runtime.h>
#include <cuda_bf16.h>
#include <cuda.h>
#include <stdint.h>

namespace {

constexpr int SQ = 144, SK = 1024, NT = 16, NSLOT = 7;
constexpr int PIECE = 72 * 128;
constexpr int QHALF = 4 * PIECE;
constexpr int PBUF = 2 * PIECE;
constexpr int SLOT = 16384;
constexpr int OFF_Q = 0;
constexpr int OFF_P = 2 * QHALF;
constexpr int OFF_RING = OFF_P + 2 * PBUF;
constexpr int OFF_MISC = OFF_RING + NSLOT * SLOT;
constexpr int BAR_FULL = OFF_MISC;
constexpr int BAR_Q = BAR_FULL + 7 * 8;
constexpr int BAR_EMPTY = BAR_Q + 4 * 8;
constexpr int BAR_VOTE = BAR_EMPTY + 7 * 8;
constexpr int BAR_PEMPTY = BAR_VOTE + 3 * 8;
constexpr int BAR_PLAST = BAR_PEMPTY + 2 * 8;
constexpr int BAR_TOK = BAR_PLAST + 8;
constexpr int BAR_L = BAR_TOK + 4 * 8;
constexpr int BAR_OUT = BAR_L + 2 * 8;
constexpr int OFF_FLAG = OFF_MISC + 320;
constexpr int OFF_ALPHA = OFF_MISC + 352;
constexpr int OFF_RED = OFF_ALPHA + 3 * SQ * 4;
constexpr int OFF_NM = OFF_RED + 4 * SQ * 4;
constexpr int OFF_INV = OFF_NM + 160 * 4;
constexpr int OFF_END = OFF_INV + 160 * 4;
constexpr int OFF_PL = QHALF - PIECE;
constexpr int SMEM_BYTES = OFF_END;
static_assert(BAR_OUT + 64 <= OFF_FLAG && SMEM_BYTES <= 232448, "smem layout");

constexpr float SCALE_LOG2E = 0.0625f * 1.4426950408889634f;
constexpr float SAFE = 48.0f / SCALE_LOG2E;

constexpr int PACE = 77, MARGIN = 900;

__device__ __forceinline__ void mbar_init(uint32_t a, int c) { asm volatile("mbarrier.init.shared::cta.b64 [%0], %1;" ::"r"(a), "r"(c) : "memory"); }
__device__ __forceinline__ void mbar_arrive(uint32_t a) { asm volatile("mbarrier.arrive.shared::cta.b64 _, [%0];" ::"r"(a) : "memory"); }
__device__ __forceinline__ void mbar_arrive2(uint32_t a) { asm volatile("mbarrier.arrive.shared::cta.b64 _, [%0], 2;" ::"r"(a) : "memory"); }
__device__ __forceinline__ void mbar_wait(uint32_t a, uint32_t ph) {
  asm volatile(
      "{\n.reg .pred p, q;\n.reg .u32 it;\nmov.u32 it, 0;\n"
      "WAIT_LOOP:\n"
      "mbarrier.try_wait.parity.shared::cta.b64 p, [%0], %1;\n"
      "add.u32 it, it, 1;\n"
      "setp.lt.and.u32 q, it, 0x100000, !p;\n"
      "@q bra WAIT_LOOP;\n}" ::"r"(a), "r"(ph) : "memory");
}
__device__ __forceinline__ void mbar_wait2(uint32_t a0, uint32_t ph0, uint32_t a1, uint32_t ph1) {
  asm volatile(
      "{\n.reg .pred p, q;\n.reg .u32 it;\nmov.u32 it, 0;\n"
      "WAIT_LOOP:\n"
      "mbarrier.try_wait.parity.shared::cta.b64 p, [%0], %1;\n"
      "mbarrier.try_wait.parity.shared::cta.b64 q, [%2], %3;\n"
      "and.pred p, p, q;\n"
      "add.u32 it, it, 1;\n"
      "setp.lt.and.u32 q, it, 0x100000, !p;\n"
      "@q bra WAIT_LOOP;\n}" ::"r"(a0), "r"(ph0), "r"(a1), "r"(ph1) : "memory");
}
__device__ __forceinline__ void mbar_wait3(uint32_t a0, uint32_t ph0, uint32_t a1, uint32_t ph1, uint32_t a2, uint32_t ph2) {
  asm volatile(
      "{\n.reg .pred p, q, r;\n.reg .u32 it;\nmov.u32 it, 0;\n"
      "WAIT_LOOP:\n"
      "mbarrier.try_wait.parity.shared::cta.b64 p, [%0], %1;\n"
      "mbarrier.try_wait.parity.shared::cta.b64 r, [%2], %3;\n"
      "mbarrier.try_wait.parity.shared::cta.b64 q, [%4], %5;\n"
      "and.pred p, p, r;\n"
      "and.pred p, p, q;\n"
      "add.u32 it, it, 1;\n"
      "setp.lt.and.u32 q, it, 0x100000, !p;\n"
      "@q bra WAIT_LOOP;\n}" ::"r"(a0), "r"(ph0), "r"(a1), "r"(ph1), "r"(a2), "r"(ph2) : "memory");
}
__device__ __forceinline__ void init_bars(uint32_t a, int n, int cnt) {
#pragma unroll
  for (int i = 0; i < n; i++) mbar_init(a + i * 8, cnt);
}
__device__ __forceinline__ void wg_bar(int id) { asm volatile("bar.sync %0, 128;" ::"r"(id) : "memory"); }
__device__ __forceinline__ void fence_async() { asm volatile("fence.proxy.async.shared::cta;" ::: "memory"); }

__device__ __forceinline__ uint32_t desc_lo(uint32_t addr) { return ((addr & 0x3FFFF) >> 4) | (1u << 16); }
__device__ __forceinline__ uint64_t desc(uint32_t lo, uint32_t byte_off) {
  uint64_t d; asm("mov.b64 %0, {%1, %2};" : "=l"(d) : "r"(lo + (byte_off >> 4)), "r"(0x40000040u)); return d;
}
__device__ __forceinline__ void wg_fence() { asm volatile("wgmma.fence.sync.aligned;" ::: "memory"); }
__device__ __forceinline__ void wg_commit() { asm volatile("wgmma.commit_group.sync.aligned;" ::: "memory"); }
template <int N> __device__ __forceinline__ void wg_wait() { asm volatile("wgmma.wait_group.sync.aligned %0;" ::"n"(N) : "memory"); }
template <int N> __device__ __forceinline__ void reg_fence(float (&d)[N]) {
#pragma unroll
  for (int i = 0; i < N; i++) asm volatile("" : "+f"(d[i])::"memory");
}

__device__ __forceinline__ float ex2(float x) { float y; asm("ex2.approx.ftz.f32 %0, %1;" : "=f"(y) : "f"(x)); return y; }
__device__ __forceinline__ uint32_t pack_bf16(float lo, float hi) { uint32_t r; asm("cvt.rn.bf16x2.f32 %0, %1, %2;" : "=r"(r) : "f"(hi), "f"(lo)); return r; }
__device__ __forceinline__ void stsm_x4_t(uint32_t addr, uint32_t a, uint32_t b, uint32_t c, uint32_t d) {
  asm volatile("stmatrix.sync.aligned.m8n8.x4.trans.shared.b16 [%0], {%1,%2,%3,%4};" ::"r"(addr), "r"(a), "r"(b), "r"(c), "r"(d) : "memory");
}
__device__ __forceinline__ void stsm_x2_t(uint32_t addr, uint32_t a, uint32_t b) {
  asm volatile("stmatrix.sync.aligned.m8n8.x2.trans.shared.b16 [%0], {%1,%2};" ::"r"(addr), "r"(a), "r"(b) : "memory");
}
__device__ __forceinline__ float lds32(uint32_t a) { float v; asm volatile("ld.shared.f32 %0, [%1];" : "=f"(v) : "r"(a) : "memory"); return v; }
__device__ __forceinline__ float2 lds64(uint32_t a) { float2 v; asm volatile("ld.shared.v2.f32 {%0,%1}, [%2];" : "=f"(v.x), "=f"(v.y) : "r"(a) : "memory"); return v; }
__device__ __forceinline__ float4 lds128(uint32_t a) { float4 v; asm volatile("ld.shared.v4.f32 {%0,%1,%2,%3}, [%4];" : "=f"(v.x), "=f"(v.y), "=f"(v.z), "=f"(v.w) : "r"(a) : "memory"); return v; }
__device__ __forceinline__ void sts32(uint32_t a, float x) { asm volatile("st.shared.f32 [%0], %1;" ::"r"(a), "f"(x) : "memory"); }
__device__ __forceinline__ void sts64(uint32_t a, float x, float y) { asm volatile("st.shared.v2.f32 [%0], {%1,%2};" ::"r"(a), "f"(x), "f"(y) : "memory"); }
__device__ __forceinline__ void sts128(uint32_t a, float x, float y, float z, float w) { asm volatile("st.shared.v4.f32 [%0], {%1,%2,%3,%4};" ::"r"(a), "f"(x), "f"(y), "f"(z), "f"(w) : "memory"); }

__device__ __forceinline__ void wgmma_qk72(float (&d)[36], uint64_t da, uint64_t db, int scale_d){
  asm volatile("{\n.reg .pred p;\nsetp.ne.b32 p, %38, 0;\n"
  "wgmma.mma_async.sync.aligned.m64n72k16.f32.bf16.bf16 "
  "{%0, %1, %2, %3, %4, %5, %6, %7, %8, %9, %10, %11, %12, %13, %14, %15, %16, %17, %18, %19, %20, %21, %22, %23, %24, %25, %26, %27, %28, %29, %30, %31, %32, %33, %34, %35}, "
  "%36, %37, p, 1, 1, 0, 0;\n}"
  : "+f"(d[0]), "+f"(d[1]), "+f"(d[2]), "+f"(d[3]), "+f"(d[4]), "+f"(d[5]), "+f"(d[6]), "+f"(d[7]), "+f"(d[8]), "+f"(d[9]), "+f"(d[10]), "+f"(d[11]), "+f"(d[12]), "+f"(d[13]), "+f"(d[14]), "+f"(d[15]), "+f"(d[16]), "+f"(d[17]), "+f"(d[18]), "+f"(d[19]), "+f"(d[20]), "+f"(d[21]), "+f"(d[22]), "+f"(d[23]), "+f"(d[24]), "+f"(d[25]), "+f"(d[26]), "+f"(d[27]), "+f"(d[28]), "+f"(d[29]), "+f"(d[30]), "+f"(d[31]), "+f"(d[32]), "+f"(d[33]), "+f"(d[34]), "+f"(d[35])
  : "l"(da), "l"(db), "r"(scale_d));
}

__device__ __forceinline__ void wgmma_mk(float (&d)[72], uint64_t da, uint64_t db, int scale_d){
  asm volatile("{\n.reg .pred p;\nsetp.ne.b32 p, %74, 0;\n"
  "wgmma.mma_async.sync.aligned.m64n144k16.f32.bf16.bf16 "
  "{%0, %1, %2, %3, %4, %5, %6, %7, %8, %9, %10, %11, %12, %13, %14, %15, %16, %17, %18, %19, %20, %21, %22, %23, %24, %25, %26, %27, %28, %29, %30, %31, %32, %33, %34, %35, %36, %37, %38, %39, %40, %41, %42, %43, %44, %45, %46, %47, %48, %49, %50, %51, %52, %53, %54, %55, %56, %57, %58, %59, %60, %61, %62, %63, %64, %65, %66, %67, %68, %69, %70, %71}, "
  "%72, %73, p, 1, 1, 1, 0;\n}"
  : "+f"(d[0]), "+f"(d[1]), "+f"(d[2]), "+f"(d[3]), "+f"(d[4]), "+f"(d[5]), "+f"(d[6]), "+f"(d[7]), "+f"(d[8]), "+f"(d[9]), "+f"(d[10]), "+f"(d[11]), "+f"(d[12]), "+f"(d[13]), "+f"(d[14]), "+f"(d[15]), "+f"(d[16]), "+f"(d[17]), "+f"(d[18]), "+f"(d[19]), "+f"(d[20]), "+f"(d[21]), "+f"(d[22]), "+f"(d[23]), "+f"(d[24]), "+f"(d[25]), "+f"(d[26]), "+f"(d[27]), "+f"(d[28]), "+f"(d[29]), "+f"(d[30]), "+f"(d[31]), "+f"(d[32]), "+f"(d[33]), "+f"(d[34]), "+f"(d[35]), "+f"(d[36]), "+f"(d[37]), "+f"(d[38]), "+f"(d[39]), "+f"(d[40]), "+f"(d[41]), "+f"(d[42]), "+f"(d[43]), "+f"(d[44]), "+f"(d[45]), "+f"(d[46]), "+f"(d[47]), "+f"(d[48]), "+f"(d[49]), "+f"(d[50]), "+f"(d[51]), "+f"(d[52]), "+f"(d[53]), "+f"(d[54]), "+f"(d[55]), "+f"(d[56]), "+f"(d[57]), "+f"(d[58]), "+f"(d[59]), "+f"(d[60]), "+f"(d[61]), "+f"(d[62]), "+f"(d[63]), "+f"(d[64]), "+f"(d[65]), "+f"(d[66]), "+f"(d[67]), "+f"(d[68]), "+f"(d[69]), "+f"(d[70]), "+f"(d[71])
  : "l"(da), "l"(db), "r"(scale_d));
}


template <int EXPECT>
__device__ __forceinline__ void tma_load(uint32_t dst, const CUtensorMap* m, uint32_t bar, int row, int dblk) {
  if (EXPECT)
    asm volatile("{\n.reg .pred p;\nelect.sync _|p, 0xffffffff;\n"
                 "@p mbarrier.arrive.expect_tx.shared::cta.b64 _, [%2], %5;\n"
                 "@p cp.async.bulk.tensor.3d.shared::cluster.global.mbarrier::complete_tx::bytes [%0], [%1, {0,%3,%4}], [%2];\n}"
                 ::"r"(dst), "l"(m), "r"(bar), "r"(row), "r"(dblk), "n"(EXPECT) : "memory");
  else
    asm volatile("{\n.reg .pred p;\nelect.sync _|p, 0xffffffff;\n"
                 "@p cp.async.bulk.tensor.3d.shared::cluster.global.mbarrier::complete_tx::bytes [%0], [%1, {0,%3,%4}], [%2];\n}"
                 ::"r"(dst), "l"(m), "r"(bar), "r"(row), "r"(dblk) : "memory");
}
__device__ __forceinline__ void tma_store(const CUtensorMap* m, uint32_t src, int row, int dblk) {
  asm volatile("{\n.reg .pred p;\nelect.sync _|p, 0xffffffff;\n"
               "@p cp.async.bulk.tensor.3d.global.shared::cta.bulk_group [%0, {0,%2,%3}], [%1];\n}" ::"l"(m), "r"(src), "r"(row), "r"(dblk) : "memory");
}
__device__ __forceinline__ void load_kv(uint32_t sb, int slot, const CUtensorMap* m, int t, int h) {
  tma_load<SLOT>(sb + OFF_RING + slot * SLOT, m, sb + BAR_FULL + slot * 8, (blockIdx.x >> 1) * SK + (t ^ ((blockIdx.x >> 6) & 15)) * 64, 2 * h);
}
template <int Y>
__device__ __forceinline__ void load_q(uint32_t sb, const CUtensorMap* m) {
  tma_load<(Y & 1) ? 0 : 2 * PIECE>(sb + OFF_Q + Y * PIECE, m, sb + BAR_Q + (Y >> 1) * 8, blockIdx.x * SQ + (Y >> 2) * 72, Y & 3);
}

__device__ __forceinline__ uint32_t piece_off(int h, int k) { return k < 3 ? OFF_Q + h * (QHALF + PIECE) + k * PIECE : OFF_RING + (2 + h) * SLOT; }
__device__ __forceinline__ void load_inv(float (&inv)[18], uint32_t a) {
#pragma unroll
  for (int g = 0; g < 4; g++) { const float4 v = lds128(a + g * 16); inv[4 * g] = v.x; inv[4 * g + 1] = v.y; inv[4 * g + 2] = v.z; inv[4 * g + 3] = v.w; }
  const float2 v = lds64(a + 64); inv[16] = v.x; inv[17] = v.y;
}
__device__ __forceinline__ void stage_piece(const float* o, const float (&inv)[18], uint32_t addr, uint32_t bar, int lane) {
#pragma unroll
  for (int g = 0; g < 4; g++) {
    const float* p = o + 8 * g; const float* a = inv + 4 * g;
    stsm_x4_t(addr + g * 2048, pack_bf16(p[0] * a[0], p[1] * a[1]), pack_bf16(p[2] * a[0], p[3] * a[1]),
              pack_bf16(p[4] * a[2], p[5] * a[3]), pack_bf16(p[6] * a[2], p[7] * a[3]));
  }
  stsm_x2_t(addr + 8192, pack_bf16(o[32] * inv[16], o[33] * inv[17]), pack_bf16(o[34] * inv[16], o[35] * inv[17]));
  __syncwarp();
  if (lane == 0) mbar_arrive(bar);
}

__global__ void __launch_bounds__(512, 1)
gqa_attn_kernel(const char* __restrict__ qp, const __grid_constant__ CUtensorMap tm_q, const __grid_constant__ CUtensorMap tm_k,
                const __grid_constant__ CUtensorMap tm_v, const __grid_constant__ CUtensorMap tm_o) {
  asm volatile("{\n.reg .pred p;\nsetp.lt.u32 p, %1, %2;\n@p prefetch.global.L2 [%0];\n}" ::"l"(qp + (blockIdx.x * (SQ * 4) + threadIdx.x) * 128u), "r"(threadIdx.x), "n"(144) : "memory");
  extern __shared__ __align__(1024) uint8_t smem_raw[];
  const uint32_t sb = (uint32_t)__cvta_generic_to_shared(smem_raw);
  const int wid = __shfl_sync(0xffffffff, threadIdx.x >> 5, 0);
  const int wg = wid >> 2, warp = wid & 3;
  const int lane = threadIdx.x & 31;
  const uint32_t clk0 = (uint32_t)clock();
#define PACE_WAIT(kb) while ((int)((uint32_t)clock() - clk0) < (kb) * PACE - MARGIN) {}

  if (wid == 8) {
    if (lane == 0) {
      init_bars(sb + BAR_Q, 4, 1);
      asm volatile("fence.mbarrier_init.release.cluster;" ::: "memory");
    }
    __syncwarp();
    load_q<0>(sb, &tm_q);
    load_q<1>(sb, &tm_q);
  } else if (lane == 0) {
    if (wid == 9) init_bars(sb + BAR_FULL, NSLOT, 1);
    if (wid == 10) init_bars(sb + BAR_EMPTY, NSLOT, 8);
    if (wid == 11) { init_bars(sb + BAR_VOTE, 6, 8); sts128(sb + OFF_FLAG, 0.f, 0.f, 0.f, 0.f); sts64(sb + OFF_FLAG + 16, 0.f, 0.f); }
    if (wid == 12) { asm volatile("prefetch.tensormap [%0];" ::"l"(&tm_k) : "memory"); init_bars(sb + BAR_TOK, 6, 4); }
    if (wid == 13) asm volatile("prefetch.tensormap [%0];" ::"l"(&tm_v) : "memory");
    if (wid == 14) asm volatile("prefetch.tensormap [%0];" ::"l"(&tm_o) : "memory");
    if (wid == 15) init_bars(sb + BAR_OUT, 8, 4);
    asm volatile("fence.mbarrier_init.release.cluster;" ::: "memory");
  }
  __syncthreads();

  const uint32_t tr_off = (8 * (lane >> 4) + (lane & 7)) * 128 + (((2 * warp + ((lane >> 3) & 1)) ^ (lane & 7)) << 4);
  const uint32_t d0 = desc_lo(sb), dring = d0 + (OFF_RING >> 4);

  if (wg < 2) {
    asm volatile("setmaxnreg.dec.sync.aligned.u32 80;");
    float s[36], l[18];
#pragma unroll
    for (int i = 0; i < 18; i++) l[i] = 0.f;
    const int tid = threadIdx.x & 127;
    const uint32_t vq = sb + (lane & 3) * 144 + wg * 72;
    const uint32_t p_addr = sb + wg * PIECE + tr_off;
    const uint32_t dq = d0 + ((OFF_Q + wg * QHALF) >> 4);
    int slot = 0; uint32_t ph = 0;
    uint32_t general = 0;
    mbar_wait(sb + BAR_Q + wg * 16, 0);
    for (int t = 0; t < NT; t++) {
      int slot_b = slot + 1; uint32_t ph_b = ph;
      if (slot_b == NSLOT) { slot_b = 0; ph_b ^= 1; }
      const uint32_t ka = dring + slot * (SLOT >> 4), kb = dring + slot_b * (SLOT >> 4);
      const uint32_t tok_next = sb + BAR_TOK + ((wg == 1 && t == 0) ? 0 : (wg + 1) * 8);
      const bool special = t < 2 || t == NT - 1;
      const bool early = wg == 0 && t == 1;
      mbar_wait3(sb + BAR_FULL + slot * 8, ph, sb + BAR_FULL + (t < 2 ? slot : slot_b) * 8, ph_b, sb + BAR_TOK + wg * 8, (t + 1 + wg) & 1);
      reg_fence(s);
      wg_fence();
#pragma unroll
      for (int k = 0; k < 8; k++) wgmma_qk72(s, desc(ka, (k >> 2) * 8192 + (k & 3) * 32), desc(dq, (k >> 2) * PIECE + (k & 3) * 32), k > 0 ? 1 : general);
      wg_commit();
      if (special) {
        if (t == 0) mbar_wait(sb + BAR_Q + wg * 16 + 8, 0); else fence_async();
        if (early) { __syncwarp(); if (lane == 0) mbar_arrive(tok_next); }
        if (t < 2) mbar_wait(sb + BAR_FULL + slot_b * 8, ph_b);
      }
      wg_fence();
#pragma unroll
      for (int k = 0; k < 8; k++) {
        wgmma_qk72(s, desc(kb, (k >> 2) * 8192 + (k & 3) * 32), desc(dq, (2 + (k >> 2)) * PIECE + (k & 3) * 32), 1);
        if (k == 5 && lane == 0 && !early) mbar_arrive(tok_next);
      }
      wg_commit();
      wg_wait<1>();
      if (t < NT - 1 && lane == 0) mbar_arrive(sb + BAR_EMPTY + slot * 8);
      const int pb = (t == NT - 1) ? 2 : (t & 1);
      if (t < NT - 1) mbar_wait(sb + BAR_PEMPTY + (t & 1) * 8, ((t >> 1) & 1) ^ 1);
      wg_wait<0>();
      reg_fence(s);
      if (t < NT - 1 && lane == 0) mbar_arrive(sb + BAR_EMPTY + slot_b * 8);

      int mx0 = __vimax3_s32(__float_as_int(s[0]), __float_as_int(s[1]), __float_as_int(s[2]));
      int mx1 = __vimax3_s32(__float_as_int(s[3]), __float_as_int(s[4]), __float_as_int(s[5]));
      int mx2 = __vimax3_s32(__float_as_int(s[6]), __float_as_int(s[7]), __float_as_int(s[8]));
      int mx3 = __vimax3_s32(__float_as_int(s[9]), __float_as_int(s[10]), __float_as_int(s[11]));
#pragma unroll
      for (int j = 12; j < 36; j += 8) {
        mx0 = __vimax3_s32(mx0, __float_as_int(s[j]), __float_as_int(s[j + 1]));
        mx1 = __vimax3_s32(mx1, __float_as_int(s[j + 2]), __float_as_int(s[j + 3]));
        mx2 = __vimax3_s32(mx2, __float_as_int(s[j + 4]), __float_as_int(s[j + 5]));
        mx3 = __vimax3_s32(mx3, __float_as_int(s[j + 6]), __float_as_int(s[j + 7]));
      }
      uint32_t mine = max(__vimax3_s32(mx0, mx1, mx2), mx3) > __float_as_int(SAFE);
      if (t == 0) {
        uint32_t mn = 0;
#pragma unroll
        for (int j = 0; j < 36; j += 4) mn = __vimax3_u32(mn, __float_as_uint(s[j]), __float_as_uint(s[j + 1]));
        mine |= mn > __float_as_uint(-SAFE);
      }
      uint32_t need;
      asm volatile("{\n.reg .pred p, q;\nsetp.ne.u32 p, %1, 0;\nbar.red.or.pred q, %2, 128, p;\nselp.u32 %0, 1, 0, q;\n}" : "=r"(need) : "r"(mine), "r"(1 + wg) : "memory");
      if (__builtin_expect(need, 0)) {
#pragma unroll
        for (int j = 0; j < 9; j++) {
          float a = fmaxf(s[4 * j + 0], s[4 * j + 2]), b = fmaxf(s[4 * j + 1], s[4 * j + 3]);
#pragma unroll
          for (int o = 4; o < 32; o <<= 1) { a = fmaxf(a, __shfl_xor_sync(0xffffffff, a, o)); b = fmaxf(b, __shfl_xor_sync(0xffffffff, b, o)); }
          if (lane < 4) sts64(vq + OFF_RED + warp * SQ * 4 + j * 8, a, b);
        }
        wg_bar(1 + wg);
        if (tid < 36) {
          const uint32_t e = (tid / 9) * 144 + wg * 72 + (tid % 9) * 8;
          float a = (t == 0) ? -INFINITY : 0.f, b = a;
#pragma unroll
          for (int w = 0; w < 4; w++) { float2 v = lds64(sb + OFF_RED + w * SQ * 4 + e); a = fmaxf(a, v.x); b = fmaxf(b, v.y); }
          float2 old = make_float2(0.f, 0.f);
          const uint32_t en = sb + OFF_NM + (tid / 9) * 160 + wg * 80 + (tid % 9) * 8;
          if (general) old = lds64(en);
          sts64(en, old.x - a, old.y - b);
          sts64(sb + OFF_RED + e, -a, -b);
          sts64(sb + OFF_ALPHA + pb * SQ * 4 + e, (t == 0) ? 0.f : ex2(-a * SCALE_LOG2E), (t == 0) ? 0.f : ex2(-b * SCALE_LOG2E));
          if (tid == 0) sts32(sb + OFF_FLAG + pb * 8 + wg * 4, __int_as_float(t));
        }
        wg_bar(1 + wg);
#pragma unroll
        for (int j = 0; j < 9; j++) {
          const float2 d = lds64(vq + OFF_RED + j * 8);
          const float2 a = lds64(vq + OFF_ALPHA + pb * SQ * 4 + j * 8);
          s[4 * j + 0] += d.x; s[4 * j + 1] += d.y; s[4 * j + 2] += d.x; s[4 * j + 3] += d.y;
          l[2 * j] *= a.x; l[2 * j + 1] *= a.y;
        }
        wg_bar(1 + wg);
        general = 1;
      }
      if (lane == 0) mbar_arrive(sb + BAR_VOTE + pb * 8);
      const uint32_t pa = p_addr + ((t == NT - 1) ? OFF_PL : OFF_P + (t & 1) * PBUF);
#pragma unroll
      for (int j = 0; j < 8; j += 2) {
        float* p = s + 4 * j;
#pragma unroll
        for (int e = 0; e < 8; e++) p[e] = ex2(p[e] * SCALE_LOG2E);
        l[2 * j + 0] += p[0]; l[2 * j + 1] += p[1]; l[2 * j + 2] += p[4]; l[2 * j + 3] += p[5];
        l[2 * j + 0] += p[2]; l[2 * j + 1] += p[3]; l[2 * j + 2] += p[6]; l[2 * j + 3] += p[7];
        stsm_x4_t(pa + j * 1024, pack_bf16(p[0], p[1]), pack_bf16(p[2], p[3]), pack_bf16(p[4], p[5]), pack_bf16(p[6], p[7]));
      }
      {
        float* p = s + 32;
#pragma unroll
        for (int e = 0; e < 4; e++) p[e] = ex2(p[e] * SCALE_LOG2E);
        l[16] += p[0]; l[17] += p[1]; l[16] += p[2]; l[17] += p[3];
        stsm_x2_t(pa + 8 * 1024, pack_bf16(p[0], p[1]), pack_bf16(p[2], p[3]));
      }
      if (t != 0 && t != NT - 2) fence_async();
      __syncwarp();
      if (__builtin_expect(general, 0)) {
        const uint32_t nm = sb + OFF_NM + (lane & 3) * 160 + wg * 80;
#pragma unroll
        for (int g = 0; g < 4; g++) {
          const float4 n = lds128(nm + g * 16);
          s[8 * g + 0] = s[8 * g + 2] = n.x; s[8 * g + 1] = s[8 * g + 3] = n.y;
          s[8 * g + 4] = s[8 * g + 6] = n.z; s[8 * g + 5] = s[8 * g + 7] = n.w;
        }
        const float2 n = lds64(nm + 64);
        s[32] = s[34] = n.x; s[33] = s[35] = n.y;
      }
      slot += (t == 0) ? 2 : 4;
      if (slot >= NSLOT) { slot -= NSLOT; ph ^= 1; }
    }
    if (lane == 0) mbar_arrive(sb + BAR_PLAST);
    {
      const bool u4 = lane & 16, u3 = lane & 8, u2 = lane & 4;
      float a[10], b[6], c[3];
#pragma unroll
      for (int i = 0; i < 9; i++) a[i] = (u4 ? l[9 + i] : l[i]) + __shfl_xor_sync(0xffffffff, u4 ? l[i] : l[9 + i], 16);
      a[9] = 0.f;
#pragma unroll
      for (int i = 0; i < 5; i++) b[i] = (u3 ? a[5 + i] : a[i]) + __shfl_xor_sync(0xffffffff, u3 ? a[i] : a[5 + i], 8);
      b[5] = 0.f;
#pragma unroll
      for (int i = 0; i < 3; i++) c[i] = (u2 ? b[3 + i] : b[i]) + __shfl_xor_sync(0xffffffff, u2 ? b[i] : b[3 + i], 4);
      const uint32_t r = vq + OFF_RED + warp * SQ * 4 + ((u4 ? 9 : 0) + (u3 ? 5 : 0) + (u2 ? 3 : 0)) * 4;
      sts32(r, c[0]);
      if (!(u2 && u3)) sts32(r + 4, c[1]);
      if (!u2) sts32(r + 8, c[2]);
    }
    const uint32_t e = sb + OFF_RED + warp * 144 + wg * 72 + lane * 4;
    wg_bar(1 + wg);
    if (lane < 18) {
      const float x0 = lds32(e), x1 = lds32(e + SQ * 4), x2 = lds32(e + 2 * SQ * 4), x3 = lds32(e + 3 * SQ * 4);
      float r; asm("rcp.approx.ftz.f32 %0, %1;" : "=f"(r) : "f"((x0 + x1) + (x2 + x3)));
      sts32(sb + OFF_INV + warp * 160 + wg * 80 + lane * 4, r);
    }
    __syncwarp();
    if (lane == 0) mbar_arrive(sb + BAR_L + wg * 8);
    if (warp == 0) {
#pragma unroll
      for (int k = 0; k < 4; k++) {
        mbar_wait(sb + BAR_OUT + (wg * 4 + k) * 8, 0);
        fence_async();
        tma_store(&tm_o, sb + piece_off(wg, k), blockIdx.x * SQ + (k & 1) * 72, 2 * wg + (k >> 1));
      }
      asm volatile("cp.async.bulk.commit_group;\ncp.async.bulk.wait_group.read 0;" ::: "memory");
    }
  } else {
    asm volatile("setmaxnreg.inc.sync.aligned.u32 176;");
    const int h = wg - 2;
    if (wid == 8) {
      PACE_WAIT(18); load_kv(sb, 0, &tm_k, 0, 0);
      PACE_WAIT(26); load_q<2>(sb, &tm_q);
      PACE_WAIT(35); load_q<3>(sb, &tm_q);
      PACE_WAIT(44); load_kv(sb, 1, &tm_k, 0, 1);
      PACE_WAIT(52); load_q<4>(sb, &tm_q);
      PACE_WAIT(61); load_q<5>(sb, &tm_q);
      PACE_WAIT(70); load_q<6>(sb, &tm_q);
      PACE_WAIT(79); load_q<7>(sb, &tm_q);
      PACE_WAIT(84); load_kv(sb, 2, &tm_k, 1, 0);
      PACE_WAIT(92); load_kv(sb, 3, &tm_k, 1, 1);
      PACE_WAIT(104); load_kv(sb, 4, &tm_v, 0, 0);
      PACE_WAIT(112); load_kv(sb, 5, &tm_v, 0, 1);
      PACE_WAIT(120); load_kv(sb, 6, &tm_k, 2, 0);
    }
    if (warp == 1) {
      mbar_wait(sb + BAR_EMPTY + h * 8, 0);
      PACE_WAIT(128 + 8 * h);
      load_kv(sb, h, h ? &tm_v : &tm_k, 2 - h, 1 - h);
    }
    float o0[72], o1[72];
    int slot = 4 + h; uint32_t ph = 0;
    const uint32_t vq = sb + (lane & 3) * 144;
    bool deferred = false;
    for (int t = 0;; t++) {
      const int pb = (t == NT - 1) ? 2 : (t & 1);
      mbar_wait(sb + BAR_VOTE + pb * 8, (t == NT - 1) ? 0 : (t >> 1) & 1);
      const float2 flag = lds64(sb + OFF_FLAG + pb * 8);
      const bool f0 = __float_as_int(flag.x) == t, f1 = __float_as_int(flag.y) == t;
      if (__builtin_expect(t > 0 && __any_sync(0xffffffff, f0 || f1), 0)) {
        wg_wait<0>();
        reg_fence(o0); reg_fence(o1);
#pragma unroll
        for (int j = 0; j < 18; j++) {
          float2 a = lds64(vq + OFF_ALPHA + pb * SQ * 4 + j * 8);
          if (!(j < 9 ? f0 : f1)) a = make_float2(1.f, 1.f);
          o0[4 * j] *= a.x; o0[4 * j + 1] *= a.y; o0[4 * j + 2] *= a.x; o0[4 * j + 3] *= a.y;
          o1[4 * j] *= a.x; o1[4 * j + 1] *= a.y; o1[4 * j + 2] *= a.x; o1[4 * j + 3] *= a.y;
        }
        reg_fence(o0); reg_fence(o1);
      }
      if (t == NT - 1) break;
      if (h == 1 && t == NT - 3) {
        mbar_wait2(sb + BAR_VOTE, 1, sb + BAR_VOTE + 16, 0);
        const float2 g0 = lds64(sb + OFF_FLAG), g1 = lds64(sb + OFF_FLAG + 16);
        deferred = !__any_sync(0xffffffff, __float_as_int(g0.x) == NT - 2 || __float_as_int(g0.y) == NT - 2 ||
                                           __float_as_int(g1.x) == NT - 1 || __float_as_int(g1.y) == NT - 1);
        if (deferred) break;
      }
      const uint32_t va = dring + slot * (SLOT >> 4), pd = d0 + ((OFF_P + (t & 1) * PBUF) >> 4);
      const bool late = h == 1 && t == NT - 2;
      mbar_wait2(sb + BAR_FULL + slot * 8, ph, late ? sb + BAR_PLAST : sb + BAR_TOK + wg * 8, t & 1);
      wg_fence();
#pragma unroll
      for (int k = 0; k < 4; k++) wgmma_mk(o0, desc(va, k * 2048), desc(pd, k * 32), (t > 0) || (k > 0));
#pragma unroll
      for (int k = 0; k < 4; k++) wgmma_mk(o1, desc(va, 8192 + k * 2048), desc(pd, k * 32), (t > 0) || (k > 0));
      wg_commit();
      if (t < NT - 2 - h) {
        if (lane == 0) mbar_arrive(sb + BAR_TOK + ((h == 0 && t != NT - 3) ? 24 : 0));
        if (h == 0 && warp >= 2) {
          int ks = slot + warp - 4; uint32_t kph = ph;
          if (ks < 0) { ks += NSLOT; kph ^= 1; }
          mbar_wait(sb + BAR_EMPTY + ks * 8, kph);
          load_kv(sb, ks, (warp == 2 || t == NT - 3) ? &tm_v : &tm_k, warp == 2 ? t + 1 : min(t + 3, NT - 1), 3 - warp);
        }
        wg_wait<0>();
        if (lane == 0) { mbar_arrive(sb + BAR_PEMPTY + (t & 1) * 8); mbar_arrive2(sb + BAR_EMPTY + slot * 8); }
        if (warp == 1) {
          mbar_wait(sb + BAR_EMPTY + slot * 8, ph);
          load_kv(sb, slot, (h || t == NT - 3) ? &tm_v : &tm_k, min(t + 3 - h, NT - 1), 1 - h);
        }
      }
      slot += 4;
      if (slot >= NSLOT) { slot -= NSLOT; ph ^= 1; }
    }
    const uint32_t v15 = dring + (h ? 0 : 6) * (SLOT >> 4);
    const uint32_t o_addr = sb + tr_off, iq = sb + OFF_INV + (lane & 3) * 160, bar_out = sb + BAR_OUT + h * 32;
    float inva[18], invb[18];
    auto pv_deferred = [&](float (&o)[72], int k, int off) {
      wgmma_mk(o, desc(d0, OFF_RING + (k < 4 ? 1 : k < 8 ? 5 : 0) * SLOT + off + (k & 3) * 2048),
               desc(d0, (k < 4 ? OFF_P + PBUF : k < 8 ? OFF_P : OFF_PL) + (k & 3) * 32), 1);
    };
    if (deferred) {
      mbar_wait2(sb + BAR_FULL + 8, 0, sb + BAR_FULL + 40, 0);
      mbar_wait2(sb + BAR_FULL, 1, sb + BAR_TOK + 24, 1);
      wg_fence();
#pragma unroll
      for (int k = 0; k < 12; k++) pv_deferred(o0, k, 0);
      wg_commit();
#pragma unroll
      for (int k = 0; k < 3; k++) pv_deferred(o1, k, 8192);
      wg_commit();
      mbar_wait(sb + BAR_L, 0);
      load_inv(inva, iq);
      wg_wait<1>();
    } else {
      mbar_wait2(sb + BAR_FULL + (h ? 0 : 48), h, sb + BAR_PLAST, 0);
      wg_fence();
#pragma unroll
      for (int k = 0; k < 4; k++) wgmma_mk(o0, desc(v15, k * 2048), desc(d0, OFF_PL + k * 32), 1);
      wg_commit();
      mbar_wait(sb + BAR_L, 0);
      load_inv(inva, iq);
      wg_wait<0>();
    }
    reg_fence(o0);
    stage_piece(o0, inva, o_addr + piece_off(h, 0), bar_out, lane);
    mbar_wait(sb + BAR_L + 8, 0);
    load_inv(invb, iq + 80);
    stage_piece(o0 + 36, invb, o_addr + piece_off(h, 1), bar_out + 8, lane);
    if (deferred) {
      wg_fence();
#pragma unroll
      for (int k = 3; k < 8; k++) pv_deferred(o1, k, 8192);
    }
    wg_fence();
#pragma unroll
    for (int k = 0; k < 4; k++) wgmma_mk(o1, desc(v15, 8192 + k * 2048), desc(d0, OFF_PL + k * 32), 1);
    wg_commit();
    wg_wait<0>();
    reg_fence(o1);
    stage_piece(o1, inva, o_addr + piece_off(h, 2), bar_out + 16, lane);
    if (h == 0 && lane == 0) mbar_arrive(sb + BAR_TOK + 24);
    stage_piece(o1 + 36, invb, o_addr + piece_off(h, 3), bar_out + 24, lane);
  }
}

typedef CUresult (*EncodeFn)(CUtensorMap*, CUtensorMapDataType, cuuint32_t, void*, const cuuint64_t*, const cuuint64_t*,
                             const cuuint32_t*, const cuuint32_t*, CUtensorMapInterleave, CUtensorMapSwizzle,
                             CUtensorMapL2promotion, CUtensorMapFloatOOBfill);

void make_map(EncodeFn enc, CUtensorMap* m, void* p, uint64_t rows, uint32_t box_rows, uint32_t box_blks) {
  cuuint64_t gd[3] = {64, rows, 4};
  cuuint64_t gs[2] = {512, 128};
  cuuint32_t bd[3] = {64, box_rows, box_blks};
  cuuint32_t es[3] = {1, 1, 1};
  enc(m, CU_TENSOR_MAP_DATA_TYPE_BFLOAT16, 3, p, gd, gs, bd, es, CU_TENSOR_MAP_INTERLEAVE_NONE, CU_TENSOR_MAP_SWIZZLE_128B,
      CU_TENSOR_MAP_L2_PROMOTION_L2_128B, CU_TENSOR_MAP_FLOAT_OOB_FILL_NONE);
}

}

extern "C" void kernel_launch(void* const* d_in, const int* in_sizes, int n_in, void* d_out, int out_size) {
  static EncodeFn enc = nullptr;
  if (!enc) {
    cudaDriverEntryPointQueryResult qr;
    cudaGetDriverEntryPoint("cuTensorMapEncodeTiled", (void**)&enc, cudaEnableDefault, &qr);
    cudaFuncSetAttribute(gqa_attn_kernel, cudaFuncAttributeMaxDynamicSharedMemorySize, SMEM_BYTES);
  }
  CUtensorMap tq, tk, tv, to;
  make_map(enc, &tq, d_in[0], 128 * SQ, 72, 1);
  make_map(enc, &tk, d_in[1], 64 * SK, 64, 2);
  make_map(enc, &tv, d_in[2], 64 * SK, 64, 2);
  make_map(enc, &to, d_out, 128 * SQ, 72, 1);
  gqa_attn_kernel<<<128, 512, SMEM_BYTES>>>((const char*)d_in[0], tq, tk, tv, to);
}
```
